```python
import torch

def _softmax(x, axis=-1):
    return torch.softmax(x, dim=axis)
def _gelu(x):
    return torch.nn.functional.gelu(x, approximate="tanh")
def _silu(x):
    return torch.nn.functional.silu(x)
def _sigmoid(x):
    return torch.sigmoid(x)
def _layernorm(x, axis=-1, eps=1e-5):
    m = x.mean(dim=axis, keepdim=True)
    v = x.var(dim=axis, keepdim=True, unbiased=False)
    return (x - m) / torch.sqrt(v + eps)
def _scatter_add(tgt, idx, src, axis=0):
    return tgt.clone().index_add_(axis, idx, src)
def _segment_sum(src, seg, n):
    out = torch.zeros((n,) + src.shape[1:], dtype=src.dtype)
    return out.index_add_(0, seg, src)
def _pad(x, pw):
    flat = tuple(v for pair in reversed(pw) for v in pair)
    return torch.nn.functional.pad(x, flat)

kernel_name = 'concat_heads__mha_block_cached__mha_block_cached__near_ridge'

def setup_inputs():

    _w = (lambda a: (lambda t: t.to(torch.bfloat16) if t.is_floating_point() else t)(torch.as_tensor(a)))
    def _A_setup():
        B, Sq, D = 8, 192, 1024
        H, Sk, Dh = 32, 1024, 128
        return {
            "x": _w((lambda *s: torch.randn(*s, dtype=torch.bfloat16) * 0.8)(B, Sq, D)),
            "k_cache": _w((lambda *s: torch.randn(*s, dtype=torch.bfloat16) * 0.8)(B, H, Sk, Dh)),
            "v_cache": _w((lambda *s: torch.randn(*s, dtype=torch.bfloat16) * 0.05)(B, H, Sk, Dh)),
            "wq": _w((lambda *s: torch.randn(*s, dtype=torch.bfloat16) * 0.8)(D, H * Dh) * (D ** -0.5)),
            "wo": _w((lambda *s: torch.randn(*s, dtype=torch.bfloat16) * 0.05)(H * Dh, D) * ((H * Dh) ** -0.5)),
        }
    _A_in = _A_setup()

    def _B_setup():
        B, Sq, D = 8, 192, 1024
        H, Sk, Dh = 32, 1024, 128
        return {
            "x": _w((lambda *s: torch.randn(*s, dtype=torch.bfloat16) * 0.8)(B, Sq, D)),
            "k_cache": _w((lambda *s: torch.randn(*s, dtype=torch.bfloat16) * 0.8)(B, H, Sk, Dh)),
            "v_cache": _w((lambda *s: torch.randn(*s, dtype=torch.bfloat16) * 0.05)(B, H, Sk, Dh)),
            "wq": _w((lambda *s: torch.randn(*s, dtype=torch.bfloat16) * 0.8)(D, H * Dh) * (D ** -0.5)),
            "wo": _w((lambda *s: torch.randn(*s, dtype=torch.bfloat16) * 0.05)(H * Dh, D) * ((H * Dh) ** -0.5)),
        }
    _B_in = _B_setup()

    return {
        "A_x": _A_in["x"],
        "A_k_cache": _A_in["k_cache"],
        "A_v_cache": _A_in["v_cache"],
        "A_wq": _A_in["wq"],
        "A_wo": _A_in["wo"],
        "B_x": _B_in["x"],
        "B_k_cache": _B_in["k_cache"],
        "B_v_cache": _B_in["v_cache"],
        "B_wq": _B_in["wq"],
        "B_wo": _B_in["wo"],
    }

def reference(A_x, A_k_cache, A_v_cache, A_wq, A_wo, B_x, B_k_cache, B_v_cache, B_wq, B_wo):
    def _A_ref(x, k_cache, v_cache, wq, wo):
        B, Sq, D = x.shape
        H, Dh = 32, 128
        q = (lambda x, *d: x.permute(*d))((x @ wq).reshape(B, Sq, H, Dh), 0, 2, 1, 3)
        scores = torch.einsum("bhqd,bhkd->bhqk", q, k_cache) * (Dh ** -0.5)
        p = _softmax(scores, axis=-1)
        o = torch.einsum("bhqk,bhkd->bhqd", p, v_cache)
        return (lambda x, *d: x.permute(*d))(o, 0, 2, 1, 3).reshape(B, Sq, H * Dh) @ wo

    def _B_ref(x, k_cache, v_cache, wq, wo):
        B, Sq, D = x.shape
        H, Dh = 32, 128
        q = (lambda x, *d: x.permute(*d))((x @ wq).reshape(B, Sq, H, Dh), 0, 2, 1, 3)
        scores = torch.einsum("bhqd,bhkd->bhqk", q, k_cache) * (Dh ** -0.5)
        p = _softmax(scores, axis=-1)
        o = torch.einsum("bhqk,bhkd->bhqd", p, v_cache)
        return (lambda x, *d: x.permute(*d))(o, 0, 2, 1, 3).reshape(B, Sq, H * Dh) @ wo

    a = _A_ref(A_x, A_k_cache, A_v_cache, A_wq, A_wo)
    b = _B_ref(B_x, B_k_cache, B_v_cache, B_wq, B_wo)
    return torch.concatenate([a, b], axis=-1)
```

```cpp
#include <cuda_runtime.h>
#include <cuda_bf16.h>
#include <cuda.h>
#include <stdint.h>
#include <type_traits>

namespace {

constexpr int SQ = 192, DM = 1024, NH = 32, SK = 1024, DH = 128, NB = 8;
constexpr int NSLOT = 4;
constexpr int SLOT_BYTES = 40960;
constexpr int A_BYTES = 192 * 64 * 2;
constexpr int Q_BYTES = 3 * 16384;
constexpr uint32_t SMEM_BASE = 1024;
constexpr int SMEM_Q = 0;
constexpr int SMEM_RING = Q_BYTES;
constexpr int SMEM_SPARE = SMEM_RING + NSLOT * SLOT_BYTES;
constexpr int SMEM_BAR = SMEM_SPARE + 16384;
constexpr int SMEM_TOTAL = SMEM_BAR + 256;

constexpr int PVA = 3;
constexpr int DEPK = 4;
constexpr int U0_READ = 48 + 16 + 3;
constexpr int EARLY = 2;

struct Params {
    CUtensorMap x[2], wq[2], k[2], v[2], wo[2];
    CUtensorMap o_st, o_ld, out;
    const __nv_bfloat16* kp[2];
    const __nv_bfloat16* vp[2];
    uint32_t sched[8], pf[8], rng[8];
    uint32_t st_pace, st_pace_chain;
    uint32_t one;
};

__device__ __align__(1024) __nv_bfloat16 g_o[2 * NB * SQ * NH * DH];
__device__ unsigned int g_cnt[16 * 32];

__device__ __forceinline__ uint32_t smem_u32(const void* p) { return (uint32_t)__cvta_generic_to_shared(p); }
__device__ __forceinline__ void mbar_init(uint32_t bar, uint32_t cnt) {
    asm volatile("mbarrier.init.shared::cta.b64 [%0], %1;" ::"r"(bar), "r"(cnt));
}
__device__ __forceinline__ void mbar_expect_tx(uint32_t bar, uint32_t bytes) {
    asm volatile("mbarrier.arrive.expect_tx.shared::cta.b64 _, [%0], %1;" ::"r"(bar), "r"(bytes) : "memory");
}
__device__ __forceinline__ void mbar_arrive(uint32_t bar) {
    asm volatile("mbarrier.arrive.shared::cta.b64 _, [%0];" ::"r"(bar) : "memory");
}
__device__ __forceinline__ void mbar_arrive_if(uint32_t bar, uint32_t cond) {
    asm volatile("{ .reg .pred p, q; setp.ne.u32 q, %1, 0; elect.sync _|p, 0xffffffff; and.pred p, p, q;\n"
                 "@p mbarrier.arrive.shared::cta.b64 _, [%0]; }" ::"r"(bar), "r"(cond) : "memory");
}
__device__ __forceinline__ void mbar_arrive_remote_if(uint32_t remote_bar, uint32_t cond) {
    asm volatile("{ .reg .pred p, q; setp.ne.u32 q, %1, 0; elect.sync _|p, 0xffffffff; and.pred p, p, q;\n"
                 "@p mbarrier.arrive.shared::cluster.b64 _, [%0]; }" ::"r"(remote_bar), "r"(cond) : "memory");
}
__device__ __forceinline__ void mbar_wait(uint32_t bar, uint32_t parity) {
    asm volatile("{ .reg .pred p; .reg .u32 n;\n"
                 "mbarrier.try_wait.parity.shared::cta.b64 p, [%0], %1;\n"
                 "@p bra DONE;\n"
                 "mov.u32 n, 0;\n"
                 "LOOP: mbarrier.try_wait.parity.shared::cta.b64 p, [%0], %1, 2000;\n"
                 "@p bra DONE;\n"
                 "add.u32 n, n, 1;\n"
                 "setp.lt.u32 p, n, 0x100000;\n"
                 "@p bra LOOP;\n"
                 "trap;\n"
                 "DONE: }" ::"r"(bar), "r"(parity) : "memory");
}
__device__ __forceinline__ void tma2d(uint32_t dst, const CUtensorMap* m, int c0, int c1, uint32_t bar) {
    asm volatile("cp.async.bulk.tensor.2d.shared::cluster.global.mbarrier::complete_tx::bytes [%0], [%1, {%3, %4}], [%2];"
                 ::"r"(dst), "l"(m), "r"(bar), "r"(c0), "r"(c1) : "memory");
}
__device__ __forceinline__ void tma2d_mc(uint32_t dst, const CUtensorMap* m, int c0, int c1, uint32_t bar) {
    asm volatile("cp.async.bulk.tensor.2d.shared::cluster.global.mbarrier::complete_tx::bytes.multicast::cluster"
                 " [%0], [%1, {%3, %4}], [%2], %5;"
                 ::"r"(dst), "l"(m), "r"(bar), "r"(c0), "r"(c1), "h"((uint16_t)3) : "memory");
}
__device__ __forceinline__ void tma3d(uint32_t dst, const CUtensorMap* m, int c0, int c1, int c2, uint32_t bar) {
    asm volatile("cp.async.bulk.tensor.3d.shared::cluster.global.mbarrier::complete_tx::bytes"
                 " [%0], [%1, {%3, %4, %5}], [%2];"
                 ::"r"(dst), "l"(m), "r"(bar), "r"(c0), "r"(c1), "r"(c2) : "memory");
}
__device__ __forceinline__ void tma_kv(uint32_t dst, const CUtensorMap* m, int group, uint32_t bar) {
    asm volatile("{ .reg .b64 pol; createpolicy.fractional.L2::evict_first.b64 pol, 1.0;\n"
                 "cp.async.bulk.tensor.4d.shared::cluster.global.mbarrier::complete_tx::bytes.L2::cache_hint"
                 " [%0], [%1, {%3, %3, %3, %4}], [%2], pol; }"
                 ::"r"(dst), "l"(m), "r"(bar), "r"(0), "r"(group) : "memory");
}
__device__ __forceinline__ void tma2d_store(const CUtensorMap* m, int c0, int c1, uint32_t src) {
    asm volatile("cp.async.bulk.tensor.2d.global.shared::cta.bulk_group [%0, {%2, %3}], [%1];"
                 ::"l"(m), "r"(src), "r"(c0), "r"(c1) : "memory");
}
__device__ __forceinline__ void tma2d_reduce_add(const CUtensorMap* m, int c0, int c1, uint32_t src) {
    asm volatile("cp.reduce.async.bulk.tensor.2d.global.shared::cta.add.bulk_group [%0, {%2, %3}], [%1];"
                 ::"l"(m), "r"(src), "r"(c0), "r"(c1) : "memory");
}
__device__ __forceinline__ bool elect_one() {
    uint32_t p;
    asm volatile("{ .reg .pred p; elect.sync _|p, 0xffffffff; selp.u32 %0, 1, 0, p; }" : "=r"(p));
    return p;
}
__device__ __forceinline__ void st_shared(uint32_t a, uint32_t v) { asm volatile("st.volatile.shared.u32 [%0], %1;" ::"r"(a), "r"(v) : "memory"); }
__device__ __forceinline__ uint32_t ld_shared_volatile(uint32_t a) {
    uint32_t v;
    asm volatile("ld.volatile.shared.u32 %0, [%1];" : "=r"(v) : "r"(a) : "memory");
    return v;
}
__device__ __forceinline__ void wait_progress(uint32_t prog, int n, uint32_t ns) {
#pragma unroll 1
    for (int it = 0; it < (1 << 20) && (int)ld_shared_volatile(prog) < n; it++) __nanosleep(ns);
}
__device__ __forceinline__ void l2_prefetch(const void* p) { asm volatile("prefetch.global.L2 [%0];" ::"l"(p) : "memory"); }
__device__ __forceinline__ void wait_count(const unsigned int* c, uint32_t target) {
    asm volatile("{ .reg .pred p; .reg .u32 v, n; mov.u32 n, 0;\n"
                 "LOOP: ld.acquire.gpu.global.u32 v, [%0];\n"
                 "setp.ge.u32 p, v, %1; @p bra DONE;\n"
                 "nanosleep.u32 200; add.u32 n, n, 1; setp.lt.u32 p, n, 0x400000; @p bra LOOP;\n"
                 "trap;\n"
                 "DONE: fence.proxy.async; }" ::"l"(c), "r"(target) : "memory");
}
__device__ __forceinline__ void wg_fence() { asm volatile("wgmma.fence.sync.aligned;" ::: "memory"); }
__device__ __forceinline__ void wg_commit() { asm volatile("wgmma.commit_group.sync.aligned;" ::: "memory"); }
template <int N> __device__ __forceinline__ void wg_wait() {
    asm volatile("wgmma.wait_group.sync.aligned %0;" ::"n"(N) : "memory");
}
__device__ __forceinline__ void bar_sync(int id, int n) { asm volatile("bar.sync %0, %1;" ::"r"(id), "r"(n) : "memory"); }
__device__ __forceinline__ void bar_arrive(int id, int n) { asm volatile("bar.arrive %0, %1;" ::"r"(id), "r"(n) : "memory"); }
__device__ __forceinline__ void sched_fence(uint32_t scratch) {
    asm volatile("{ .reg .u32 c; mov.u32 c, %%clock; st.shared.u32 [%0], c; }" ::"r"(scratch) : "memory");
}
__device__ __forceinline__ void fence_async_smem() { asm volatile("fence.proxy.async.shared::cta;" ::: "memory"); }

__host__ __device__ constexpr uint32_t desc_lo(uint32_t off, uint32_t lbo) { return ((SMEM_BASE + off) >> 4) | ((lbo >> 4) << 16); }
#define DESC_HI "0x40000040"
constexpr uint32_t HI_KV = 0x40000080, HI_W = 0x40000040;

#define R8(d, o) "+f"(d[o + 0]), "+f"(d[o + 1]), "+f"(d[o + 2]), "+f"(d[o + 3]), "+f"(d[o + 4]), "+f"(d[o + 5]), "+f"(d[o + 6]), "+f"(d[o + 7])
#define R64(d) R8(d, 0), R8(d, 8), R8(d, 16), R8(d, 24), R8(d, 32), R8(d, 40), R8(d, 48), R8(d, 56)
#define W8(d, o) "=f"(d[o + 0]), "=f"(d[o + 1]), "=f"(d[o + 2]), "=f"(d[o + 3]), "=f"(d[o + 4]), "=f"(d[o + 5]), "=f"(d[o + 6]), "=f"(d[o + 7])
#define W64(d) W8(d, 0), W8(d, 8), W8(d, 16), W8(d, 24), W8(d, 32), W8(d, 40), W8(d, 48), W8(d, 56)
#define S64 "%0,%1,%2,%3,%4,%5,%6,%7,%8,%9,%10,%11,%12,%13,%14,%15,%16,%17,%18,%19,%20,%21,%22,%23,%24,%25,%26,%27,%28,%29,%30,%31," \
            "%32,%33,%34,%35,%36,%37,%38,%39,%40,%41,%42,%43,%44,%45,%46,%47,%48,%49,%50,%51,%52,%53,%54,%55,%56,%57,%58,%59,%60,%61,%62,%63"

template <int TB, uint32_t A_LO, uint32_t B_LO>
__device__ __forceinline__ void wgmma_ss(float (&d)[64], uint32_t a_var) {
    asm volatile("{ .reg .b32 lo; .reg .b64 da, db; add.u32 lo, %64, %65; mov.b64 da, {lo, " DESC_HI "}; mov.b64 db, {%66, %68};\n"
                 "wgmma.mma_async.sync.aligned.m64n128k16.f32.bf16.bf16 {" S64 "}, da, db, 1, 1, 1, 0, %67; }"
                 : R64(d) : "r"(a_var), "n"(A_LO), "n"(B_LO), "n"(TB), "n"(TB ? HI_W : HI_KV));
}
template <int TB, uint32_t A_LO, uint32_t B_LO>
__device__ __forceinline__ void wgmma_ss_init(float (&d)[64], uint32_t a_var) {
    asm volatile("{ .reg .b32 lo; .reg .b64 da, db; add.u32 lo, %64, %65; mov.b64 da, {lo, " DESC_HI "}; mov.b64 db, {%66, %68};\n"
                 "wgmma.mma_async.sync.aligned.m64n128k16.f32.bf16.bf16 {" S64 "}, da, db, 0, 1, 1, 0, %67; }"
                 : W64(d) : "r"(a_var), "n"(A_LO), "n"(B_LO), "n"(TB), "n"(TB ? HI_W : HI_KV));
}
template <int TB, uint32_t B_LO>
__device__ __forceinline__ void wgmma_rs(float (&d)[64], uint32_t a0, uint32_t a1, uint32_t a2, uint32_t a3) {
    asm volatile("{ .reg .b64 db; mov.b64 db, {%68, %70};\n"
                 "wgmma.mma_async.sync.aligned.m64n128k16.f32.bf16.bf16 {" S64 "}, {%64,%65,%66,%67}, db, 1, 1, 1, %69; }"
                 : R64(d) : "r"(a0), "r"(a1), "r"(a2), "r"(a3), "n"(B_LO), "n"(TB), "n"(HI_KV));
}
template <int TB, uint32_t B_LO>
__device__ __forceinline__ void wgmma_rs_sc(float (&d)[64], uint32_t a0, uint32_t a1, uint32_t a2, uint32_t a3, uint32_t acc) {
    asm volatile("{ .reg .b64 db; .reg .pred p; setp.ne.u32 p, %70, 0; mov.b64 db, {%68, %71};\n"
                 "wgmma.mma_async.sync.aligned.m64n128k16.f32.bf16.bf16 {" S64 "}, {%64,%65,%66,%67}, db, p, 1, 1, %69; }"
                 : R64(d) : "r"(a0), "r"(a1), "r"(a2), "r"(a3), "n"(B_LO), "n"(TB), "r"(acc), "n"(HI_KV));
}
template <int I> using IC = std::integral_constant<int, I>;
template <int I, int N, class F>
__device__ __forceinline__ void static_for(F&& f) {
    if constexpr (I < N) {
        f(std::integral_constant<int, I>{});
        static_for<I + 1, N>(f);
    }
}
__device__ __forceinline__ void reg_fence(float (&d)[64]) {
#pragma unroll
    for (int i = 0; i < 64; i++) asm volatile("" : "+f"(d[i])::"memory");
}
__device__ __forceinline__ uint32_t pack_bf16(float lo, float hi) {
    uint32_t r;
    asm("cvt.rn.bf16x2.f32 %0, %1, %2;" : "=r"(r) : "f"(hi), "f"(lo));
    return r;
}
__device__ __forceinline__ float ex2(float x) {
    float y;
    asm("ex2.approx.ftz.f32 %0, %1;" : "=f"(y) : "f"(x));
    return y;
}

template <int C0 = 0, int C1 = 8>
__device__ __forceinline__ void store_tile(const float (&d)[64], float s0, float s1, uint32_t base) {
    uint32_t t;
    asm volatile("mov.u32 %0, %%tid.x;" : "=r"(t));
    const uint32_t row = ((t >> 5) & 3) * 16 + (t & 15);
    const uint32_t st_addr = base + row * 128 + ((((t >> 4) & 1) ^ (t & 7)) << 4);
#pragma unroll
    for (int c = C0; c < C1; c++) {
        uint32_t r0 = pack_bf16(d[8 * c + 0] * s0, d[8 * c + 1] * s0);
        uint32_t r1 = pack_bf16(d[8 * c + 2] * s1, d[8 * c + 3] * s1);
        uint32_t r2 = pack_bf16(d[8 * c + 4] * s0, d[8 * c + 5] * s0);
        uint32_t r3 = pack_bf16(d[8 * c + 6] * s1, d[8 * c + 7] * s1);
        uint32_t a = (st_addr ^ ((c & 3) << 5)) + (c >> 2) * 8192;
        asm volatile("stmatrix.sync.aligned.m8n8.x4.shared.b16 [%0], {%1,%2,%3,%4};"
                     ::"r"(a), "r"(r0), "r"(r1), "r"(r2), "r"(r3) : "memory");
    }
}

__device__ __forceinline__ void add_tile(float (&d)[64], uint32_t base) {
    uint32_t t;
    asm volatile("mov.u32 %0, %%tid.x;" : "=r"(t));
    const uint32_t row = ((t >> 5) & 3) * 16 + (t & 15);
    const uint32_t ld_addr = base + row * 128 + ((((t >> 4) & 1) ^ (t & 7)) << 4);
#pragma unroll
    for (int c = 0; c < 8; c++) {
        uint32_t r[4];
        asm volatile("ldmatrix.sync.aligned.m8n8.x4.shared.b16 {%0,%1,%2,%3}, [%4];"
                     : "=r"(r[0]), "=r"(r[1]), "=r"(r[2]), "=r"(r[3]) : "r"((ld_addr ^ ((c & 3) << 5)) + (c >> 2) * 8192) : "memory");
#pragma unroll
        for (int i = 0; i < 4; i++) {
            d[8 * c + 2 * i] += __uint_as_float(r[i] << 16);
            d[8 * c + 2 * i + 1] += __uint_as_float(r[i] & 0xffff0000u);
        }
    }
}

__global__ void __cluster_dims__(2, 1, 1) __launch_bounds__(512, 1)
fused_mha_kernel(const __grid_constant__ Params P) {
    extern __shared__ __align__(1024) uint8_t smem_raw[];
    const uint32_t sb = smem_u32(smem_raw);
    if ((sb & 0xFFFFFFu) != SMEM_BASE) asm volatile("trap;");
    const uint32_t full = sb + SMEM_BAR, empty = full + 32, pempty = full + 64, stfree = full + 128, prog = full + 136;
    const uint32_t dummy = full + 144, rdone = full + 152, oready = full + 160;
    const int wg = __shfl_sync(0xffffffffu, threadIdx.x >> 7, 0);
    const int job = blockIdx.x >> 3, j8 = blockIdx.x & 7;
    const int br = job >> 3, b = job & 7;
    const uint32_t rank = blockIdx.x & 1;
    auto item_br = [&](int r) { return r >> 1; };
    auto item_h = [&](int r) { return (r & 1) * 16 + br * 8 + j8; };
    auto o_row = [&](int branch, int chunk) { return ((branch * 8 + b) * 64 + (branch == 0 && chunk >= 48 ? chunk - 48 : chunk)) * SQ; };
    const uint32_t sched = P.sched[br * 4 + (j8 >> 1)];
    auto unit = [&](int u) { return (int)(sched >> (16 + 4 * u)) & 3; };
    auto o_halves = [&](int r) { return (int)((sched & 0xffff) >> (4 * r)) & 7; };
    auto q_ahead = [&](int r) { return (sched >> (4 * r + 3)) & 1; };
    auto q_count = [&](int r) { return (int)(1 + q_ahead(r) - ((sched << 1 >> (4 * r)) & 1)); };

    if (threadIdx.x == 384) {
        asm volatile("prefetch.tensormap [%0];" ::"l"(&P.wq[item_br(0)]) : "memory");
        asm volatile("prefetch.tensormap [%0];" ::"l"(&P.x[item_br(0)]) : "memory");
#pragma unroll
        for (int i = 0; i < NSLOT; i++) {
            mbar_init(full + 8 * i, 1);
            mbar_init(empty + 8 * i, 3);
            mbar_init(pempty + 8 * i, 3);
            mbar_init(oready + 16 * i, 1);
            mbar_init(oready + 16 * i + 8, 1);
        }
        mbar_init(stfree, 1);
        mbar_init(rdone, 1);
        st_shared(prog, 0);
        asm volatile("fence.mbarrier_init.release.cluster;" ::: "memory");
    }
    __syncthreads();
    asm volatile("barrier.cluster.arrive.relaxed.aligned;" ::: "memory");
    if (threadIdx.x == 384) {
#pragma unroll
        for (int k = 0; k < EARLY; k++) {
            const uint32_t slot = sb + SMEM_RING + k * SLOT_BYTES;
            mbar_expect_tx(full + 8 * k, SLOT_BYTES);
            tma2d(slot, &P.x[0], k * 64, b * SQ, full + 8 * k);
            tma3d(slot + A_BYTES, &P.wq[0], 0, k * 64, item_h(0) * 2, full + 8 * k);
            tma2d(slot + A_BYTES / 2, &P.x[0], k * 64, b * SQ + 96, full + 8 * k);
        }
    }
    __syncwarp();
    asm volatile("barrier.cluster.wait.aligned;" ::: "memory");

    if (wg == 3) {
        asm volatile("setmaxnreg.dec.sync.aligned.u32 32;");
        const int warp = __shfl_sync(0xffffffffu, threadIdx.x >> 5, 0);
        if (warp == 12) {
            if (elect_one()) {
                int ou = 0;
                uint32_t n = 0;
#pragma unroll 1
                for (int r = 0; r < 5; r++) {
                    const int nq = r < 4 ? q_count(r) : 0;
#pragma unroll 1
                    for (int q = r; q < r + nq; q++) {
                        const int h = item_h(q), ab = item_br(q);
#pragma unroll 1
                        for (int k = 0; k < 16; k++) {
                            const int s = k & 3;
                            const uint32_t slot = sb + SMEM_RING + s * SLOT_BYTES, par = ((k >> 2) & 1) ^ 1;
                            if (n >= EARLY) {
                                mbar_wait(empty + 8 * s, par);
                                mbar_expect_tx(full + 8 * s, SLOT_BYTES);
                                tma3d(slot + A_BYTES, &P.wq[ab], 0, k * 64, h * 2, full + 8 * s);
                                mbar_wait(pempty + 8 * s, par);
                                tma2d_mc(slot + rank * (A_BYTES / 2), &P.x[ab], k * 64, b * SQ + rank * 96, full + 8 * s);
                            }
                            st_shared(prog, ++n);
                        }
                    }
                    const int oend = r < 4 ? ou + o_halves(r) : 8;
#pragma unroll 1
                    for (int k = ou * 8; k < oend * 8; k++) {
                        const int s = k & 3;
                        const uint32_t slot = sb + SMEM_RING + s * SLOT_BYTES, par = ((k >> 2) & 1) ^ 1;
                        mbar_wait(empty + 8 * s, par);
                        if (n == U0_READ) mbar_arrive(rdone);
                        mbar_expect_tx(full + 8 * s, SLOT_BYTES);
                        const int kc = (unit(k >> 4) * 16 + (k & 15)) * 64;
                        tma3d(slot + A_BYTES, &P.wo[br], 0, kc, j8 * 2, full + 8 * s);
                        if ((k & 7) == 0) {
                            mbar_wait(oready + k, 0);
                        }
                        mbar_wait(pempty + 8 * s, par);
                        tma2d_mc(slot + rank * (A_BYTES / 2), &P.o_ld, 0, o_row(br, kc >> 6) + rank * 96, full + 8 * s);
                        st_shared(prog, ++n);
                    }
                    ou = oend;
                    if (r < 4) {
                        const int h = item_h(r), ab = item_br(r);
                        const int row0 = (b * NH + h) * SK;
#pragma unroll 1
                        for (int t = 0; t < 16; t++) {
                            const int s = t & 3;
                            const uint32_t slot = sb + SMEM_RING + s * SLOT_BYTES;
                            mbar_wait(empty + 8 * s, ((t >> 2) & 1) ^ 1);
                            if (n == U0_READ) mbar_arrive(rdone);
                            mbar_expect_tx(full + 8 * s, 32768);
                            tma_kv(slot + (t & 1) * 8192, (t & 1) ? &P.v[ab] : &P.k[ab], row0 / 8 + (t >> 1) * 16, full + 8 * s);
                            st_shared(prog, ++n);
                        }
                    }
                }
            }
        } else if (warp == 13) {
            const int lane = threadIdx.x & 31, cls = br * 4 + (j8 >> 1);
#pragma unroll 1
            for (int r = 0, n = 0; r < 4; r++) {
                const int np = 16 * q_count(r) + 8 * o_halves(r);
                const int per = ((P.pf[cls] >> (8 * r)) & 255) * 8;
                if (per && np) {
                    const int rng = P.rng[cls] >> (8 * r), t0 = rng & 15, sh = (rng >> 4) & 3;
                    const size_t off = (size_t)(b * NH + item_h(r)) * SK * DH + lane * 64;
#pragma unroll 1
                    for (int k = 0; k < 16; k++) {
                        const int t = t0 + (k >> sh);
                        const __nv_bfloat16* p = ((t & 1) ? P.vp[item_br(r)] : P.kp[item_br(r)]) + off + (t >> 1) * 128 * DH + (k & ((1 << sh) - 1)) * per * 64;
                        wait_progress(prog, n + k + 1, 100);
#pragma unroll
                        for (int i = 0; i < 4; i++)
                            if (lane + 32 * i < per) l2_prefetch(p + i * 2048);
                    }
                }
                n += np + 16;
            }
        } else if (warp == 14) {
#pragma unroll 1
            for (int r = 0, n0 = 0; r < 4; r++) {
                n0 += 16 + 16 * q_count(r) + 8 * o_halves(r);
                if (r == 1 && br == 1) {
                    if ((threadIdx.x & 31) == 0) {
                        wait_progress(prog, n0 - 2, 1000);
                        wait_count(g_cnt + b * 32 + 9, 8);
                    }
                    __syncwarp();
                }
                const uint32_t dl = q_ahead(r) ? P.st_pace_chain : P.st_pace >> (8 * r);
#pragma unroll 1
                for (int i = 0; i < 12; i++) {
                    const int w = i >> 2;
                    if ((i & 3) == 0) bar_sync(4 + w, 160);
                    wait_progress(prog, n0 + (dl & 15) + (i * ((dl >> 4) & 15) >> 2), 100);
                    if ((threadIdx.x & 31) == 0)
                        tma2d_store(&P.o_st, 0, o_row(item_br(r), item_h(r) * 2 + (i & 1)) + (i >> 1) * 32,
                                    sb + SMEM_Q + w * 16384 + (i & 1) * 8192 + (i & 2) * 2048);
                    __syncwarp();
                }
                if ((threadIdx.x & 31) == 0) {
                    asm volatile("cp.async.bulk.commit_group;" ::: "memory");
                    asm volatile("cp.async.bulk.wait_group.read 0;" ::: "memory");
                    mbar_arrive(stfree);
                    asm volatile("cp.async.bulk.wait_group 0;" ::: "memory");
                    asm volatile("red.release.gpu.global.add.u32 [%0], 1;"
                                 ::"l"(g_cnt + (item_br(r) * 8 + b) * 32 + (item_h(r) >> 2)) : "memory");
                }
                __syncwarp();
            }
        } else if (elect_one()) {
            unsigned int* cnt = g_cnt + job * 32;
#pragma unroll 1
            for (int r = 0, u = 0, n0 = 0; r < 5; r++) {
                n0 += r < 4 ? 16 * q_count(r) : 0;
                const int uend = r < 4 ? u + o_halves(r) : 8;
#pragma unroll 1
                for (; u < uend; u++, n0 += 8) {
                    wait_progress(prog, n0 - 16, 3000);
                    wait_count(cnt + unit(u >> 1) * 2 + (u & 1), 4);
                    mbar_arrive(oready + 8 * u);
                }
                if (r == 1 && br == 0) {
                    mbar_wait(rdone, 0);
                    asm volatile("red.release.gpu.global.add.u32 [%0], 1;" ::"l"(cnt + 9) : "memory");
                }
                n0 += 16;
            }
            if (atomicAdd(cnt + 8, 1u) == 7u) {
#pragma unroll
                for (int i = 0; i < 10; i++) cnt[i] = 0;
            }
        }
    } else {
        asm volatile("setmaxnreg.inc.sync.aligned.u32 160;");
        const uint32_t lead = __shfl_sync(0xffffffffu, (threadIdx.x & 127) == 0, 0);
        uint32_t peer_sb;
        asm("mapa.shared::cluster.u32 %0, %1, %2;" : "=r"(peer_sb) : "r"(sb), "r"(rank ^ 1));
        const uint32_t qbase = sb + SMEM_Q + wg * 16384;
        const float sc = 0.08838834764831845f * 1.4426950408889634f;
        const uint32_t one = P.one;
        float s[64], o[64];
#pragma unroll
        for (int i = 0; i < 64; i++) o[i] = 0.f;

        const int nxt = wg == 2 ? 0 : wg + 1, prv = wg == 0 ? 2 : wg - 1;
        auto token_wait = [&]() { bar_sync(7 + wg, 256); };
        auto token_pass = [&](int to) { bar_arrive(7 + to, 256); };
        if (wg == 1) token_pass(0);
        auto release = [&](int slot, bool mc) {
            mbar_arrive_if(empty + 8 * slot, lead);
            mbar_arrive_remote_if(peer_sb + SMEM_BAR + 64 + 8 * slot, lead && mc);
        };
        auto proj_stage = [&](float (&acc)[64], auto S, auto INIT, uint32_t parity) {
            constexpr int sl = S.value;
            mbar_wait(full + 8 * sl, parity);
            wg_fence();
            static_for<0, 4>([&](auto KK) {
                constexpr int kk = KK.value;
                constexpr uint32_t da = desc_lo(SMEM_RING + sl * SLOT_BYTES + kk * 32, 16);
                constexpr uint32_t db = desc_lo(SMEM_RING + sl * SLOT_BYTES + A_BYTES + kk * 2048, 8192);
                if constexpr (INIT.value == 1 && kk == 0) wgmma_ss_init<1, da, db>(acc, wg * 512);
                else wgmma_ss<1, da, db>(acc, wg * 512);
            });
            wg_commit();
        };
        auto proj_rest = [&](float (&acc)[64], int nk4, bool more, int to, int r) {
            proj_stage(acc, IC<2>{}, IC<0>{}, 0);
            proj_stage(acc, IC<3>{}, IC<0>{}, 0);
            wg_wait<1>();
            release(2, true);
#pragma unroll 1
            for (int k4 = 1; k4 < nk4 - 1; k4++) {
                static_for<0, 4>([&](auto S) {
                    proj_stage(acc, S, IC<0>{}, k4 & 1);
                    wg_wait<1>();
                    release((S.value + 3) & 3, true);
                });
            }
            proj_stage(acc, IC<0>{}, IC<0>{}, 1);
            wg_wait<1>();
            release(3, true);
            if (r == 4) {
                if (wg == 1 && nk4 != 16) {
                    wg_wait<0>();
                    reg_fence(acc);
                    add_tile(acc, sb + SMEM_SPARE);
                    reg_fence(acc);
                }
                token_wait();
            }
            proj_stage(acc, IC<1>{}, IC<0>{}, 1);
            wg_wait<1>();
            release(0, more);
            if (r != 4) {
                wg_wait<0>();
                release(1, more);
                if (!more) token_wait();
            }
            proj_stage(acc, IC<2>{}, IC<0>{}, 1);
            wg_wait<1>();
            proj_stage(acc, IC<3>{}, IC<0>{}, 1);
            if (!more && to >= 0) token_pass(to);
            wg_wait<1>();
            release(2, more);
            if (r < 5) mbar_wait(stfree, (r & 1) ^ 1);
            wg_wait<0>();
            reg_fence(acc);
            release(3, more);
        };
        auto out_tile = [&](uint32_t base, bool add) {
            if (lead && elect_one()) {
                const int c0 = br * DM + j8 * 128, c1 = b * SQ + wg * 64;
                if (add) {
                    tma2d_reduce_add(&P.out, c0, c1, base);
                    tma2d_reduce_add(&P.out, c0 + 64, c1, base + 8192);
                } else {
                    tma2d_store(&P.out, c0, c1, base);
                    tma2d_store(&P.out, c0 + 64, c1, base + 8192);
                }
                asm volatile("cp.async.bulk.commit_group;" ::: "memory");
            }
        };
        const uint32_t poff = wg == 1 ? SMEM_SPARE : SMEM_RING + wg * SLOT_BYTES + 32768;
        int odone = 0;
        float l0 = 0.f, l1 = 0.f;
        auto recip_l = [&]() {
            l0 += __shfl_xor_sync(0xffffffffu, l0, 1);
            l1 += __shfl_xor_sync(0xffffffffu, l1, 1);
            l0 += __shfl_xor_sync(0xffffffffu, l0, 2);
            l1 += __shfl_xor_sync(0xffffffffu, l1, 2);
            l0 = __fdividef(1.f, l0); l1 = __fdividef(1.f, l1);
        };
        proj_stage(s, IC<0>{}, IC<1>{}, 0);
        proj_stage(s, IC<1>{}, IC<0>{}, 0);
        wg_wait<1>();
        release(0, true);
        wg_wait<0>();
        release(1, true);
#pragma unroll 1
        for (int r = 0;; r++) {
            const int on = o_halves(r);
            bool qa = q_ahead(r);
            const bool extra = on || qa;
            proj_rest(s, r < 4 ? 4 : 16 - 2 * odone, extra, r < 4 ? (wg == 1 ? 0 : 1) : (wg == 2 ? -1 : nxt), r);
            if (r == 4) break;
            if (extra) {
                proj_stage(o, IC<0>{}, IC<1>{}, 0);
                proj_stage(o, IC<1>{}, IC<0>{}, 0);
                sched_fence(dummy);
                reg_fence(s);
                store_tile(s, 1.f, 1.f, qbase);
                sched_fence(dummy);
                wg_wait<1>();
                release(0, true);
                fence_async_smem();
                wg_wait<0>();
                release(1, true);
                proj_rest(o, qa ? 4 : 2 * on, false, wg == 1 ? 0 : 1, 9);
                if (wg != 1) {
                    mbar_wait(empty + 8 * wg, 1);
                    mbar_wait(empty + 8 * wg + 8, 1);
                }
                store_tile(o, 1.f, 1.f, sb + poff);
                mbar_wait(full, 0);
                token_wait();
            } else {
                store_tile(s, 1.f, 1.f, qbase);
                mbar_wait(full, 0);
                fence_async_smem();
                token_wait();
            }
            bool chained = false;
        next_head:

            float b0, b1;
            const bool hold = chained && wg == 0;
            const uint32_t qd0 = (chained ? poff : SMEM_Q + wg * 16384) >> 4;
#pragma unroll 1
            for (int j2 = 0; j2 < 4; j2++) {
                static_for<0, 2>([&](auto JJ) {
                    constexpr int jj = JJ.value;
                    constexpr int sk = 2 * jj, sv = 2 * jj + 1;
                    const bool first = jj == 0 && j2 == 0;
                    uint32_t p[32];
                    auto qk = [&]() {
                        wg_fence();
                        wgmma_ss_init<0, desc_lo(0, 16), desc_lo(SMEM_RING + sk * SLOT_BYTES, 16)>(s, qd0);
                        static_for<1, 8>([&](auto KK) {
                            constexpr int kk = KK.value;
                            wgmma_ss<0, desc_lo((kk >> 2) * 8192 + (kk & 3) * 32, 16),
                                     desc_lo(SMEM_RING + sk * SLOT_BYTES + (kk >> 2) * 1024 + (kk & 3) * 32, 16)>(s, qd0);
                        });
                        wg_commit();
                    };
                    auto neg_max = [&](auto NC, float& a0, float& a1) {
                        a0 = fmaxf(s[0], s[1]); a1 = fmaxf(s[2], s[3]);
#pragma unroll
                        for (int c = 1; c < NC.value; c++) {
                            a0 = fmaxf(a0, fmaxf(s[4 * c], s[4 * c + 1]));
                            a1 = fmaxf(a1, fmaxf(s[4 * c + 2], s[4 * c + 3]));
                        }
                        a0 = fmaxf(a0, __shfl_xor_sync(0xffffffffu, a0, 1));
                        a1 = fmaxf(a1, __shfl_xor_sync(0xffffffffu, a1, 1));
                        a0 = fmaxf(a0, __shfl_xor_sync(0xffffffffu, a0, 2));
                        a1 = fmaxf(a1, __shfl_xor_sync(0xffffffffu, a1, 2));
                        a0 *= -sc; a1 *= -sc;
                    };
                    auto pv_range = [&](auto K0, auto K1) {
                        wg_fence();
                        static_for<K0.value, K1.value>([&](auto KK) {
                            constexpr int kk = KK.value;
                            constexpr uint32_t dv = desc_lo(SMEM_RING + sv * SLOT_BYTES + 8192 + kk * 4096, 1024);
                            if constexpr (jj == 0 && kk == 0) wgmma_rs_sc<1, dv>(o, p[0], p[1], p[2], p[3], j2);
                            else wgmma_rs<1, dv>(o, p[4 * kk], p[4 * kk + 1], p[4 * kk + 2], p[4 * kk + 3]);
                        });
                        wg_commit();
                    };
                    qk();
                    const bool entry0 = first && !chained && wg == 0;
                    token_pass(entry0 ? prv : nxt);
                    const bool last2 = j2 == 3, mc = last2 && !qa;
                    if (jj == 1) {
                        if (!(hold && last2)) release(1, mc);
                    } else {
                        mbar_arrive_if(empty + 8 * 3, lead && (j2 != 0 || chained));
                        if (extra) {
                            if (j2 == 0) {
                                if (chained) store_tile(o, l0, l1, qbase);
                            } else if (on) {
                                if (j2 == 1) { if (wg != 1) out_tile(sb + poff, false); }
                                else if (last2) asm volatile("cp.async.bulk.wait_group 0;" ::: "memory");
                            }
                        }
                    }
                    wg_wait<0>();
                    reg_fence(s);
                    if (first) {
                        neg_max(IC<2>{}, b0, b1);
                        l0 = 0.f; l1 = 0.f;
                    }
                    bool exact = false;
                    float t0, t1;
                    while (true) {
                        float x[DEPK];
#pragma unroll
                        for (int i = 0; i < DEPK; i++) x[i] = fmaf(s[i], sc, (i & 2) ? b1 : b0);
#pragma unroll
                        for (int i = 0; i < 64; i += 2) {
                            float e0 = ex2(x[i % DEPK]), e1 = ex2(x[(i + 1) % DEPK]);
                            p[i >> 1] = pack_bf16(e0, e1);
                            float& t = (i & 2) ? t1 : t0;
                            if (i < 4) t = e0 + e1;
                            else {
                                const float told = t;
                                t += e0; t += e1;
                                e0 = told;
                            }
                            if (i + DEPK < 64) {
                                const float bb = ((i + DEPK) & 2) ? b1 : b0;
                                asm("{ .reg .pred p; setp.ne.u32 p, %4, 0; @p fma.rn.f32 %0, %1, %2, %3; }" : "+f"(e0) : "f"(s[i + DEPK]), "f"(sc), "f"(bb), "r"(one));
                                asm("{ .reg .pred p; setp.ne.u32 p, %4, 0; @p fma.rn.f32 %0, %1, %2, %3; }" : "+f"(e1) : "f"(s[i + DEPK + 1]), "f"(sc), "f"(bb), "r"(one));
                                x[i % DEPK] = e0; x[(i + 1) % DEPK] = e1;
                            }
                        }
                        uint32_t redo;
                        asm volatile("{ .reg .pred p, q; setp.gtu.f32 p, %1, 0f4B800000; bar.red.or.pred q, %2, 128, p; selp.u32 %0, 1, 0, q; }"
                                     : "=r"(redo) : "f"(t0 + t1), "r"(1 + wg) : "memory");
                        if (__builtin_expect(!redo || exact, 1)) break;
                        exact = true;
                        qk();
                        wg_wait<0>();
                        reg_fence(s);
                        float a0, a1;
                        neg_max(IC<16>{}, a0, a1);
                        a0 = fminf(a0, b0); a1 = fminf(a1, b1);
                        const float al0 = ex2(a0 - b0), al1 = ex2(a1 - b1);
                        b0 = a0; b1 = a1;
                        l0 *= al0; l1 *= al1;
#pragma unroll
                        for (int c = 0; c < 16; c++) {
                            o[4 * c] *= al0; o[4 * c + 1] *= al0; o[4 * c + 2] *= al1; o[4 * c + 3] *= al1;
                        }
                    }
                    if (jj == 1 && mc) {
                        if (hold) { release(0, true); release(1, true); }
                        release(2, true);
                    }
                    mbar_wait(full + 8 * sv, j2 & 1);
                    token_wait();
                    pv_range(IC<0>{}, IC<PVA>{});
                    const bool keep = jj == 1 ? (wg != 0 && mc) : entry0;
                    if (!keep) token_pass(prv);
                    if (jj == 1) mbar_arrive_if(empty + 8 * sk, lead && !mc);
                    else if (!(hold && last2)) release(sk, mc);
                    l0 += t0; l1 += t1;
                    if (jj == 0) {
                        if (first && extra) {
                            fence_async_smem();
                            if (chained) bar_arrive(4 + wg, 160);
                        }
                    } else if (last2 && qa) recip_l();
                    if (!keep) token_wait();
                    pv_range(IC<PVA>{}, IC<8>{});
                    token_pass(nxt);
                    if (jj == 0 || !mc) {
                        mbar_wait(full + 8 * (sk ^ 2), (j2 + jj) & 1);
                        token_wait();
                    }
                    wg_wait<0>();
                    reg_fence(o);
                });
            }
            if (qa) {
                r++;
                chained = true;
                qa = false;
                goto next_head;
            }
            release(3, true);
            odone += on;
            proj_stage(s, IC<0>{}, IC<1>{}, 0);
            proj_stage(s, IC<1>{}, IC<0>{}, 0);
            sched_fence(dummy);
            reg_fence(o);
            recip_l();
            mbar_wait(stfree, (r & 1) ^ 1);
            store_tile<0, 1>(o, l0, l1, qbase);
            sched_fence(dummy);
            wg_wait<1>();
            release(0, true);
            sched_fence(dummy);
            store_tile<1, 8>(o, l0, l1, qbase);
            sched_fence(dummy);
            wg_wait<0>();
            release(1, true);
            fence_async_smem();
            bar_arrive(4 + wg, 160);
        }
        store_tile(s, 1.f, 1.f, qbase);
        fence_async_smem();
        bar_sync(1 + wg, 128);
        out_tile(qbase, odone != 0 && wg != 1);
        asm volatile("cp.async.bulk.wait_group.read 0;" ::: "memory");
    }
}

typedef CUresult (*EncodeFn)(CUtensorMap*, CUtensorMapDataType, cuuint32_t, void*, const cuuint64_t*, const cuuint64_t*,
                             const cuuint32_t*, const cuuint32_t*, CUtensorMapInterleave, CUtensorMapSwizzle,
                             CUtensorMapL2promotion, CUtensorMapFloatOOBfill);

void make_map(EncodeFn enc, CUtensorMap* m, const void* ptr, int rank, const cuuint64_t* dims, const cuuint64_t* strides,
              const cuuint32_t* box) {
    const cuuint32_t es[4] = {1, 1, 1, 1};
    enc(m, CU_TENSOR_MAP_DATA_TYPE_BFLOAT16, rank, const_cast<void*>(ptr), dims, strides, box, es,
        CU_TENSOR_MAP_INTERLEAVE_NONE, CU_TENSOR_MAP_SWIZZLE_128B, CU_TENSOR_MAP_L2_PROMOTION_L2_128B,
        CU_TENSOR_MAP_FLOAT_OOB_FILL_NONE);
}
void map2d(EncodeFn enc, CUtensorMap* m, const void* p, uint64_t rows, uint64_t cols, uint32_t box_rows) {
    const cuuint64_t dims[2] = {cols, rows};
    const cuuint64_t str[1] = {cols * 2};
    const cuuint32_t box[2] = {64, box_rows};
    make_map(enc, m, p, 2, dims, str, box);
}
void map3d(EncodeFn enc, CUtensorMap* m, const void* p, uint64_t rows, uint64_t cols, uint32_t box_rows) {
    const cuuint64_t dims[3] = {64, rows, cols / 64};
    const cuuint64_t str[2] = {cols * 2, 128};
    const cuuint32_t box[3] = {64, box_rows, 2};
    make_map(enc, m, p, 3, dims, str, box);
}

void map4d(EncodeFn enc, CUtensorMap* m, const void* p, uint64_t rows, uint64_t cols, uint32_t box_rows) {
    const cuuint64_t dims[4] = {64, 8, cols / 64, rows / 8};
    const cuuint64_t str[3] = {cols * 2, 128, cols * 16};
    const cuuint32_t box[4] = {64, 8, 2, box_rows / 8};
    make_map(enc, m, p, 4, dims, str, box);
}

const uint32_t kSched[8] = {0x20, 0x20, 0x40, 0x40, 0x808, 8, 8, 8};
const uint32_t kPf[8] = {0x0406, 0x0406, 6, 6, 0x00040004, 0x04000004, 0x04000004, 0x04000004};
const uint32_t kRng[8] = {0x18, 0x18, 0x18, 0x18, 0x10, 0x10, 0x10, 0x10};
const uint32_t kStPace = 0x35353524, kStPaceChain = 0x13;
const uint32_t kUnitOrder[8] = {0x3120, 0x3120, 0x3210, 0x3210, 0x2301, 0x2301, 0x2301, 0x2301};

}

extern "C" void kernel_launch(void* const* d_in, const int* in_sizes, int n_in, void* d_out, int out_size) {
    (void)in_sizes; (void)n_in; (void)out_size;
    void* fn = nullptr;
    cudaDriverEntryPointQueryResult q;
    cudaGetDriverEntryPoint("cuTensorMapEncodeTiled", &fn, cudaEnableDefault, &q);
    EncodeFn enc = (EncodeFn)fn;
    void* o_ptr = nullptr;
    cudaGetSymbolAddress(&o_ptr, g_o);

    Params P;
    for (int br = 0; br < 2; br++) {
        const void* x = d_in[5 * br + 0];
        const void* k = d_in[5 * br + 1];
        const void* v = d_in[5 * br + 2];
        const void* wq = d_in[5 * br + 3];
        const void* wo = d_in[5 * br + 4];
        map2d(enc, &P.x[br], x, NB * SQ, DM, 96);
        map3d(enc, &P.wq[br], wq, DM, NH * DH, 64);
        map4d(enc, &P.k[br], k, (uint64_t)NB * NH * SK, DH, 128);
        map4d(enc, &P.v[br], v, (uint64_t)NB * NH * SK, DH, 128);
        map3d(enc, &P.wo[br], wo, NH * DH, DM, 64);
        P.kp[br] = (const __nv_bfloat16*)k;
        P.vp[br] = (const __nv_bfloat16*)v;
    }
    map2d(enc, &P.o_st, o_ptr, 2 * NB * 64 * SQ, 64, 32);
    map2d(enc, &P.o_ld, o_ptr, 2 * NB * 64 * SQ, 64, 96);
    map2d(enc, &P.out, d_out, NB * SQ, 2 * DM, 64);

    for (int i = 0; i < 8; i++) { P.sched[i] = kSched[i] | kUnitOrder[i] << 16; P.pf[i] = kPf[i]; P.rng[i] = kRng[i]; }
    P.st_pace = kStPace; P.st_pace_chain = kStPaceChain;
    P.one = 1;

    cudaFuncSetAttribute(fused_mha_kernel, cudaFuncAttributeMaxDynamicSharedMemorySize, SMEM_TOTAL);
    fused_mha_kernel<<<128, 512, SMEM_TOTAL>>>(P);
}
```
